```python
import torch

def _softmax(x, axis=-1):
    return torch.softmax(x, dim=axis)
def _gelu(x):
    return torch.nn.functional.gelu(x, approximate="tanh")
def _silu(x):
    return torch.nn.functional.silu(x)
def _sigmoid(x):
    return torch.sigmoid(x)
def _layernorm(x, axis=-1, eps=1e-5):
    m = x.mean(dim=axis, keepdim=True)
    v = x.var(dim=axis, keepdim=True, unbiased=False)
    return (x - m) / torch.sqrt(v + eps)
def _scatter_add(tgt, idx, src, axis=0):
    return tgt.clone().index_add_(axis, idx, src)
def _segment_sum(src, seg, n):
    out = torch.zeros((n,) + src.shape[1:], dtype=src.dtype)
    return out.index_add_(0, seg, src)
def _pad(x, pw):
    flat = tuple(v for pair in reversed(pw) for v in pair)
    return torch.nn.functional.pad(x, flat)

kernel_name = 'recurrent_scan__softmax_full_mha__geglu_ffn__prompt'

def setup_inputs():

    _w = (lambda a: (lambda t: t.to(torch.bfloat16) if t.is_floating_point() else t)(torch.as_tensor(a)))
    def _A_setup():
        B, S, D = 1, 2048, 1024
        return {
            "x": _w((lambda *s: torch.randn(*s, dtype=torch.bfloat16) * 0.05)(B, S, D)),
            "wqkv": _w((lambda *s: torch.randn(*s, dtype=torch.bfloat16) * 0.05)(D, 3 * D)),
            "wo": _w((lambda *s: torch.randn(*s, dtype=torch.bfloat16) * 0.05)(D, D)),
        }
    _A_in = _A_setup()

    def _B_setup():
        B, S, D, F = 1, 2048, 1024, 3584
        return {
            "x": _w((lambda *s: torch.randn(*s, dtype=torch.bfloat16) * 0.05)(B, S, D)),
            "w_gate": _w((lambda *s: torch.randn(*s, dtype=torch.bfloat16) * 0.05)(D, F)),
            "w_up": _w((lambda *s: torch.randn(*s, dtype=torch.bfloat16) * 0.05)(D, F)),
            "w_down": _w((lambda *s: torch.randn(*s, dtype=torch.bfloat16) * 0.05)(F, D)),
        }
    _B_in = _B_setup()

    return {
        "A_x": _A_in["x"],
        "A_wqkv": _A_in["wqkv"],
        "A_wo": _A_in["wo"],
        "B_x": _B_in["x"],
        "B_w_gate": _B_in["w_gate"],
        "B_w_up": _B_in["w_up"],
        "B_w_down": _B_in["w_down"],
    }

def reference(A_x, A_wqkv, A_wo, B_x, B_w_gate, B_w_up, B_w_down):
    def _A_ref(x, wqkv, wo):
        B, S, D = x.shape
        H = 32; Dh = D // H
        qkv = (lambda x, *d: x.permute(*d))((x @ wqkv).reshape(B, S, 3, H, Dh), 2, 0, 3, 1, 4)
        q, k, v = qkv[0], qkv[1], qkv[2]
        scale = Dh ** -0.5
        scores = torch.einsum("bhqd,bhkd->bhqk", q, k) * scale
        p = _softmax(scores, axis=-1)
        o = torch.einsum("bhqk,bhkd->bhqd", p, v)
        return (lambda x, *d: x.permute(*d))(o, 0, 2, 1, 3).reshape(B, S, D) @ wo

    def _B_ref(x, w_gate, w_up, w_down):
        return (_gelu(x @ w_gate) * (x @ w_up)) @ w_down

    x = A_x
    xn = _layernorm(x, axis=-1)
    s = _A_ref(xn, A_wqkv, A_wo)
    g = _silu(_B_ref(xn, B_w_gate, B_w_up, B_w_down))
    return x + s * g
```

```cpp
#include <cuda_runtime.h>
#include <cuda_bf16.h>
#include <cuda.h>
#include <stdint.h>

#define DEV __device__ __forceinline__
typedef __nv_bfloat16 bf16;

constexpr int S_LEN = 2048, D_MODEL = 1024, F_DIM = 3584, N_HEADS = 32, D_HEAD = 32;

__device__ __align__(1024) bf16 g_xn[S_LEN * D_MODEL];
__device__ __align__(1024) bf16 g_qkv[S_LEN * 3 * D_MODEL];
__device__ __align__(1024) bf16 g_h[S_LEN * F_DIM];
__device__ __align__(1024) bf16 g_o[S_LEN * D_MODEL];

DEV uint32_t smem_u32(const void* p) { return (uint32_t)__cvta_generic_to_shared(p); }
DEV void mbar_init(uint32_t bar, uint32_t count) {
  asm volatile("mbarrier.init.shared::cta.b64 [%0], %1;" ::"r"(bar), "r"(count) : "memory");
}
DEV void mbar_expect_tx(uint32_t bar, uint32_t bytes) {
  asm volatile("mbarrier.arrive.expect_tx.shared::cta.b64 _, [%0], %1;" ::"r"(bar), "r"(bytes) : "memory");
}
DEV void mbar_arrive(uint32_t bar) { asm volatile("mbarrier.arrive.shared::cta.b64 _, [%0];" ::"r"(bar) : "memory"); }
DEV void mbar_arrive_cluster(uint32_t bar, uint32_t cta) {
  asm volatile(
      "{\n.reg .b32 ra;\nmapa.shared::cluster.u32 ra, %0, %1;\n"
      "mbarrier.arrive.release.cluster.shared::cluster.b64 _, [ra];\n}\n" ::"r"(bar), "r"(cta) : "memory");
}
DEV void mbar_wait(uint32_t bar, uint32_t parity) {
  uint32_t ok, spins = 0;
  do {
    asm volatile(
        "{\n.reg .pred p;\nmbarrier.try_wait.parity.shared::cta.b64 p, [%1], %2;\nselp.u32 %0, 1, 0, p;\n}\n"
        : "=r"(ok) : "r"(bar), "r"(parity) : "memory");
    if (++spins > (1u << 24)) asm volatile("trap;");
  } while (!ok);
}
DEV void cluster_sync_all() {
  asm volatile("barrier.cluster.arrive.release.aligned;\nbarrier.cluster.wait.acquire.aligned;\n" ::: "memory");
}
DEV uint32_t cluster_rank() { uint32_t r; asm volatile("mov.u32 %0, %%cluster_ctarank;" : "=r"(r)); return r; }
DEV void tma_load_2d(uint32_t dst, const CUtensorMap* map, uint32_t bar, int c0, int c1) {
  asm volatile(
      "cp.async.bulk.tensor.2d.shared::cluster.global.mbarrier::complete_tx::bytes [%0], [%1, {%3, %4}], [%2];"
      ::"r"(dst), "l"(map), "r"(bar), "r"(c0), "r"(c1) : "memory");
}
DEV void tma_load_2d_mc(uint32_t dst, const CUtensorMap* map, uint32_t bar, int c0, int c1, uint16_t mask) {
  asm volatile(
      "cp.async.bulk.tensor.2d.shared::cluster.global.mbarrier::complete_tx::bytes.multicast::cluster "
      "[%0], [%1, {%3, %4}], [%2], %5;"
      ::"r"(dst), "l"(map), "r"(bar), "r"(c0), "r"(c1), "h"(mask) : "memory");
}
DEV void prefetch_tmap(const CUtensorMap* map) {
  asm volatile("prefetch.tensormap [%0];" ::"l"(map) : "memory");
}
DEV void wgmma_fence() { asm volatile("wgmma.fence.sync.aligned;" ::: "memory"); }
DEV void wgmma_commit() { asm volatile("wgmma.commit_group.sync.aligned;" ::: "memory"); }
template <int N> DEV void wgmma_wait() { asm volatile("wgmma.wait_group.sync.aligned %0;" ::"n"(N) : "memory"); }
template <int R> DEV void reg_inc() { asm volatile("setmaxnreg.inc.sync.aligned.u32 %0;" ::"n"(R)); }
template <int R> DEV void reg_dec() { asm volatile("setmaxnreg.dec.sync.aligned.u32 %0;" ::"n"(R)); }

DEV uint64_t make_desc(uint32_t addr, uint32_t lbo, uint32_t sbo, uint32_t swz) {
  return (uint64_t)((addr & 0x3FFFF) >> 4) | ((uint64_t)(lbo >> 4) << 16) | ((uint64_t)(sbo >> 4) << 32) |
         ((uint64_t)swz << 62);
}
DEV float ex2(float x) { float y; asm("ex2.approx.ftz.f32 %0, %1;" : "=f"(y) : "f"(x)); return y; }
DEV float rcp(float x) { float y; asm("rcp.approx.ftz.f32 %0, %1;" : "=f"(y) : "f"(x)); return y; }
DEV uint32_t pack_bf16(float lo, float hi) {
  uint32_t r; asm("cvt.rn.bf16x2.f32 %0, %1, %2;" : "=r"(r) : "f"(hi), "f"(lo)); return r;
}
DEV float bf16_round(float x) { return __bfloat162float(__float2bfloat16_rn(x)); }

template<int TB>
DEV void wgmma_ss_n256(float (&d)[128], uint64_t da, uint64_t db, int sd) {
  asm volatile("{\n.reg .pred p;\nsetp.ne.b32 p, %130, 0;\n"
    "wgmma.mma_async.sync.aligned.m64n256k16.f32.bf16.bf16 "
    "{%0, %1, %2, %3, %4, %5, %6, %7, %8, %9, %10, %11, %12, %13, %14, %15, %16, %17, %18, %19, %20, %21, %22, %23, %24, %25, %26, %27, %28, %29, %30, %31, %32, %33, %34, %35, %36, %37, %38, %39, %40, %41, %42, %43, %44, %45, %46, %47, %48, %49, %50, %51, %52, %53, %54, %55, %56, %57, %58, %59, %60, %61, %62, %63, %64, %65, %66, %67, %68, %69, %70, %71, %72, %73, %74, %75, %76, %77, %78, %79, %80, %81, %82, %83, %84, %85, %86, %87, %88, %89, %90, %91, %92, %93, %94, %95, %96, %97, %98, %99, %100, %101, %102, %103, %104, %105, %106, %107, %108, %109, %110, %111, %112, %113, %114, %115, %116, %117, %118, %119, %120, %121, %122, %123, %124, %125, %126, %127}, %128, %129, p, 1, 1, 0, %131;\n}\n"
    : "+f"(d[0]), "+f"(d[1]), "+f"(d[2]), "+f"(d[3]), "+f"(d[4]), "+f"(d[5]), "+f"(d[6]), "+f"(d[7]), "+f"(d[8]), "+f"(d[9]), "+f"(d[10]), "+f"(d[11]), "+f"(d[12]), "+f"(d[13]), "+f"(d[14]), "+f"(d[15]), "+f"(d[16]), "+f"(d[17]), "+f"(d[18]), "+f"(d[19]), "+f"(d[20]), "+f"(d[21]), "+f"(d[22]), "+f"(d[23]), "+f"(d[24]), "+f"(d[25]), "+f"(d[26]), "+f"(d[27]), "+f"(d[28]), "+f"(d[29]), "+f"(d[30]), "+f"(d[31]), "+f"(d[32]), "+f"(d[33]), "+f"(d[34]), "+f"(d[35]), "+f"(d[36]), "+f"(d[37]), "+f"(d[38]), "+f"(d[39]), "+f"(d[40]), "+f"(d[41]), "+f"(d[42]), "+f"(d[43]), "+f"(d[44]), "+f"(d[45]), "+f"(d[46]), "+f"(d[47]), "+f"(d[48]), "+f"(d[49]), "+f"(d[50]), "+f"(d[51]), "+f"(d[52]), "+f"(d[53]), "+f"(d[54]), "+f"(d[55]), "+f"(d[56]), "+f"(d[57]), "+f"(d[58]), "+f"(d[59]), "+f"(d[60]), "+f"(d[61]), "+f"(d[62]), "+f"(d[63]), "+f"(d[64]), "+f"(d[65]), "+f"(d[66]), "+f"(d[67]), "+f"(d[68]), "+f"(d[69]), "+f"(d[70]), "+f"(d[71]), "+f"(d[72]), "+f"(d[73]), "+f"(d[74]), "+f"(d[75]), "+f"(d[76]), "+f"(d[77]), "+f"(d[78]), "+f"(d[79]), "+f"(d[80]), "+f"(d[81]), "+f"(d[82]), "+f"(d[83]), "+f"(d[84]), "+f"(d[85]), "+f"(d[86]), "+f"(d[87]), "+f"(d[88]), "+f"(d[89]), "+f"(d[90]), "+f"(d[91]), "+f"(d[92]), "+f"(d[93]), "+f"(d[94]), "+f"(d[95]), "+f"(d[96]), "+f"(d[97]), "+f"(d[98]), "+f"(d[99]), "+f"(d[100]), "+f"(d[101]), "+f"(d[102]), "+f"(d[103]), "+f"(d[104]), "+f"(d[105]), "+f"(d[106]), "+f"(d[107]), "+f"(d[108]), "+f"(d[109]), "+f"(d[110]), "+f"(d[111]), "+f"(d[112]), "+f"(d[113]), "+f"(d[114]), "+f"(d[115]), "+f"(d[116]), "+f"(d[117]), "+f"(d[118]), "+f"(d[119]), "+f"(d[120]), "+f"(d[121]), "+f"(d[122]), "+f"(d[123]), "+f"(d[124]), "+f"(d[125]), "+f"(d[126]), "+f"(d[127])
    : "l"(da), "l"(db), "r"(sd), "n"(TB));
}
template<int TB>
DEV void wgmma_ss_n128(float (&d)[64], uint64_t da, uint64_t db, int sd) {
  asm volatile("{\n.reg .pred p;\nsetp.ne.b32 p, %66, 0;\n"
    "wgmma.mma_async.sync.aligned.m64n128k16.f32.bf16.bf16 "
    "{%0, %1, %2, %3, %4, %5, %6, %7, %8, %9, %10, %11, %12, %13, %14, %15, %16, %17, %18, %19, %20, %21, %22, %23, %24, %25, %26, %27, %28, %29, %30, %31, %32, %33, %34, %35, %36, %37, %38, %39, %40, %41, %42, %43, %44, %45, %46, %47, %48, %49, %50, %51, %52, %53, %54, %55, %56, %57, %58, %59, %60, %61, %62, %63}, %64, %65, p, 1, 1, 0, %67;\n}\n"
    : "+f"(d[0]), "+f"(d[1]), "+f"(d[2]), "+f"(d[3]), "+f"(d[4]), "+f"(d[5]), "+f"(d[6]), "+f"(d[7]), "+f"(d[8]), "+f"(d[9]), "+f"(d[10]), "+f"(d[11]), "+f"(d[12]), "+f"(d[13]), "+f"(d[14]), "+f"(d[15]), "+f"(d[16]), "+f"(d[17]), "+f"(d[18]), "+f"(d[19]), "+f"(d[20]), "+f"(d[21]), "+f"(d[22]), "+f"(d[23]), "+f"(d[24]), "+f"(d[25]), "+f"(d[26]), "+f"(d[27]), "+f"(d[28]), "+f"(d[29]), "+f"(d[30]), "+f"(d[31]), "+f"(d[32]), "+f"(d[33]), "+f"(d[34]), "+f"(d[35]), "+f"(d[36]), "+f"(d[37]), "+f"(d[38]), "+f"(d[39]), "+f"(d[40]), "+f"(d[41]), "+f"(d[42]), "+f"(d[43]), "+f"(d[44]), "+f"(d[45]), "+f"(d[46]), "+f"(d[47]), "+f"(d[48]), "+f"(d[49]), "+f"(d[50]), "+f"(d[51]), "+f"(d[52]), "+f"(d[53]), "+f"(d[54]), "+f"(d[55]), "+f"(d[56]), "+f"(d[57]), "+f"(d[58]), "+f"(d[59]), "+f"(d[60]), "+f"(d[61]), "+f"(d[62]), "+f"(d[63])
    : "l"(da), "l"(db), "r"(sd), "n"(TB));
}
template<int TB>
DEV void wgmma_rs_n32(float (&d)[16], uint32_t a0, uint32_t a1, uint32_t a2, uint32_t a3, uint64_t db, int sd) {
  asm volatile("{\n.reg .pred p;\nsetp.ne.b32 p, %21, 0;\n"
    "wgmma.mma_async.sync.aligned.m64n32k16.f32.bf16.bf16 "
    "{%0, %1, %2, %3, %4, %5, %6, %7, %8, %9, %10, %11, %12, %13, %14, %15}, {%16, %17, %18, %19}, %20, p, 1, 1, %22;\n}\n"
    : "+f"(d[0]), "+f"(d[1]), "+f"(d[2]), "+f"(d[3]), "+f"(d[4]), "+f"(d[5]), "+f"(d[6]), "+f"(d[7]), "+f"(d[8]), "+f"(d[9]), "+f"(d[10]), "+f"(d[11]), "+f"(d[12]), "+f"(d[13]), "+f"(d[14]), "+f"(d[15])
    : "r"(a0), "r"(a1), "r"(a2), "r"(a3), "l"(db), "r"(sd), "n"(TB));
}

__global__ void __launch_bounds__(256) ln_kernel(const bf16* __restrict__ x) {
  const int row = blockIdx.x * 8 + (threadIdx.x >> 5);
  const int lane = threadIdx.x & 31;
  const uint4* src = reinterpret_cast<const uint4*>(x + (size_t)row * D_MODEL);
  float f[32];
#pragma unroll
  for (int i = 0; i < 4; i++) {
    uint4 v = __ldg(src + lane + 32 * i);
    const uint32_t w[4] = {v.x, v.y, v.z, v.w};
#pragma unroll
    for (int j = 0; j < 4; j++) {
      f[i * 8 + 2 * j] = __uint_as_float(w[j] << 16);
      f[i * 8 + 2 * j + 1] = __uint_as_float(w[j] & 0xffff0000u);
    }
  }
  float sum = 0.f;
#pragma unroll
  for (int i = 0; i < 32; i++) sum += f[i];
#pragma unroll
  for (int o = 16; o; o >>= 1) sum += __shfl_xor_sync(0xffffffffu, sum, o);
  const float mean = sum * (1.0f / D_MODEL);
  float sq = 0.f;
#pragma unroll
  for (int i = 0; i < 32; i++) { float d = f[i] - mean; sq += d * d; }
#pragma unroll
  for (int o = 16; o; o >>= 1) sq += __shfl_xor_sync(0xffffffffu, sq, o);
  const float m_b = bf16_round(mean);
  const float v_b = bf16_round(sq * (1.0f / D_MODEL));
  const float den = bf16_round(sqrtf(bf16_round(v_b + 1e-5f)));
  uint4* dst = reinterpret_cast<uint4*>(g_xn + (size_t)row * D_MODEL);
#pragma unroll
  for (int i = 0; i < 4; i++) {
    uint32_t w[4];
#pragma unroll
    for (int j = 0; j < 4; j++) {
      float a = bf16_round(f[i * 8 + 2 * j] - m_b) / den;
      float b = bf16_round(f[i * 8 + 2 * j + 1] - m_b) / den;
      w[j] = pack_bf16(a, b);
    }
    dst[lane + 32 * i] = make_uint4(w[0], w[1], w[2], w[3]);
  }
}

constexpr int G1_STAGES = 4;
constexpr int G1_A_BYTES = 128 * 64 * 2, G1_B_BYTES = 64 * 256 * 2;
constexpr int G1_STAGE_BYTES = G1_A_BYTES + G1_B_BYTES;
constexpr int G1_SMEM = G1_STAGES * G1_STAGE_BYTES + 1024 + 256;
constexpr int G1_NUM_CT = 8 * 40;

DEV float gelu_tanh(float x) {
  const float c = 2.0f * 0.7978845608028654f * 1.4426950408889634f;
  float t = x * x;
  float u = fmaf(t, 0.044715f, 1.0f);
  float z = x * u * c;
  float e = ex2(-z);
  return x * rcp(1.0f + e);
}

__global__ void __cluster_dims__(2, 1, 1) __launch_bounds__(384, 1)
gemm1_kernel(const __grid_constant__ CUtensorMap tmA, const __grid_constant__ CUtensorMap tmQKV,
             const __grid_constant__ CUtensorMap tmG, const __grid_constant__ CUtensorMap tmU) {
  extern __shared__ uint8_t smem_raw[];
  const uint32_t base = (smem_u32(smem_raw) + 1023) & ~1023u;
  const uint32_t sA = base, sB = base + G1_STAGES * G1_A_BYTES;
  const uint32_t bars = sB + G1_STAGES * G1_B_BYTES;
  auto full = [&](int s) { return bars + 8 * s; };
  auto empty = [&](int s) { return bars + 8 * (G1_STAGES + s); };
  const uint32_t rank = cluster_rank();
  const int wg = threadIdx.x >> 7;
  if (threadIdx.x == 0) {
    for (int s = 0; s < G1_STAGES; s++) { mbar_init(full(s), 1); mbar_init(empty(s), 4); }
    asm volatile("fence.mbarrier_init.release.cluster;" ::: "memory");
    asm volatile("fence.proxy.async.shared::cta;" ::: "memory");
  }
  __syncthreads();
  cluster_sync_all();
  const int n_clusters = gridDim.x >> 1, cluster_id = blockIdx.x >> 1;

  if (wg == 0) {
    reg_dec<40>();
    if (threadIdx.x == 0) {
      int s = 0; uint32_t ph = 0;
      for (int ct = cluster_id; ct < G1_NUM_CT; ct += n_clusters) {
        const int mp = ct & 7, nt = ct >> 3;
        const int m0 = (mp * 2 + rank) * 128;
        const CUtensorMap* bmap; int bcol;
        if (nt < 12) { bmap = &tmQKV; bcol = nt * 256 + rank * 128; }
        else { bmap = rank ? &tmU : &tmG; bcol = (nt - 12) * 128; }
        for (int k = 0; k < 16; k++) {
          mbar_wait(empty(s), ph ^ 1);
          mbar_expect_tx(full(s), G1_STAGE_BYTES);
          tma_load_2d(sA + s * G1_A_BYTES, &tmA, full(s), k * 64, m0);
          tma_load_2d_mc(sB + s * G1_B_BYTES + (2 * rank) * 8192, bmap, full(s), bcol, k * 64, 3);
          tma_load_2d_mc(sB + s * G1_B_BYTES + (2 * rank + 1) * 8192, bmap, full(s), bcol + 64, k * 64, 3);
          if (++s == G1_STAGES) { s = 0; ph ^= 1; }
        }
      }
    }
    __syncwarp();
    cluster_sync_all();
  } else {
    reg_inc<232>();
    const int cw = wg - 1;
    const int tid = threadIdx.x & 127, lane = tid & 31, w4 = tid >> 5;
    float acc[128];
    int s = 0; uint32_t ph = 0;
    for (int ct = cluster_id; ct < G1_NUM_CT; ct += n_clusters) {
      int prev_s = 0;
      for (int k = 0; k < 16; k++) {
        mbar_wait(full(s), ph);
        wgmma_fence();
        const uint64_t da = make_desc(sA + s * G1_A_BYTES + cw * 8192, 16, 1024, 1);
        const uint64_t db = make_desc(sB + s * G1_B_BYTES, 8192, 1024, 1);
#pragma unroll
        for (int kk = 0; kk < 4; kk++) wgmma_ss_n256<1>(acc, da + kk * 2, db + kk * 128, (k | kk) != 0);
        wgmma_commit();
        if (k > 0) {
          wgmma_wait<1>();
          if (tid < 2) mbar_arrive_cluster(empty(prev_s), tid);
        }
        prev_s = s;
        if (++s == G1_STAGES) { s = 0; ph ^= 1; }
      }
      wgmma_wait<0>();
      if (tid < 2) mbar_arrive_cluster(empty(prev_s), tid);

      const int mp = ct & 7, nt = ct >> 3;
      const int row0 = (mp * 2 + rank) * 128 + cw * 64 + w4 * 16 + (lane >> 2);
      const int cq = (lane & 3) * 2;
      if (nt < 12) {
        bf16* p0 = g_qkv + (size_t)row0 * 3072 + nt * 256 + cq;
        bf16* p1 = p0 + 8 * 3072;
#pragma unroll
        for (int j = 0; j < 32; j++) {
          *reinterpret_cast<uint32_t*>(p0 + 8 * j) = pack_bf16(acc[4 * j], acc[4 * j + 1]);
          *reinterpret_cast<uint32_t*>(p1 + 8 * j) = pack_bf16(acc[4 * j + 2], acc[4 * j + 3]);
        }
      } else {
        bf16* p0 = g_h + (size_t)row0 * F_DIM + (nt - 12) * 128 + cq;
        bf16* p1 = p0 + 8 * F_DIM;
#pragma unroll
        for (int j = 0; j < 16; j++) {
          float hv[4];
#pragma unroll
          for (int e = 0; e < 4; e++) {
            float g = bf16_round(acc[4 * j + e]);
            float u = bf16_round(acc[64 + 4 * j + e]);
            hv[e] = bf16_round(gelu_tanh(g)) * u;
          }
          *reinterpret_cast<uint32_t*>(p0 + 8 * j) = pack_bf16(hv[0], hv[1]);
          *reinterpret_cast<uint32_t*>(p1 + 8 * j) = pack_bf16(hv[2], hv[3]);
        }
      }
    }
    cluster_sync_all();
  }
}

constexpr int AT_STAGES = 4;
constexpr int AT_SMEM = 16384 + AT_STAGES * 16384 + 1024 + 256;

__global__ void __launch_bounds__(544, 1) attn_kernel(const __grid_constant__ CUtensorMap tmQKV) {
  extern __shared__ uint8_t smem_raw[];
  const uint32_t base = (smem_u32(smem_raw) + 1023) & ~1023u;
  const uint32_t sQ = base;
  auto sK = [&](int s) { return base + 16384 + s * 16384; };
  auto sV = [&](int s) { return base + 16384 + s * 16384 + 8192; };
  const uint32_t bars = base + 16384 + AT_STAGES * 16384;
  auto full = [&](int s) { return bars + 8 * s; };
  auto empty = [&](int s) { return bars + 8 * (AT_STAGES + s); };
  const uint32_t qbar = bars + 8 * 2 * AT_STAGES;
  const int head = blockIdx.x >> 3, qt = blockIdx.x & 7;
  const int warp = threadIdx.x >> 5, lane = threadIdx.x & 31;
  if (threadIdx.x == 0) {
    for (int s = 0; s < AT_STAGES; s++) { mbar_init(full(s), 1); mbar_init(empty(s), 4); }
    mbar_init(qbar, 1);
    asm volatile("fence.proxy.async.shared::cta;" ::: "memory");
  }
  __syncthreads();
  if (warp == 16) {
    if (lane == 0) {
      mbar_expect_tx(qbar, 16384);
      tma_load_2d(sQ, &tmQKV, qbar, head * 32, qt * 256);
      tma_load_2d(sQ + 8192, &tmQKV, qbar, head * 32, qt * 256 + 128);
      for (int j = 0; j < S_LEN / 128; j++) {
        const int s = j % AT_STAGES; const uint32_t ph = (j / AT_STAGES) & 1;
        mbar_wait(empty(s), ph ^ 1);
        mbar_expect_tx(full(s), 16384);
        tma_load_2d(sK(s), &tmQKV, full(s), D_MODEL + head * 32, j * 128);
        tma_load_2d(sV(s), &tmQKV, full(s), 2 * D_MODEL + head * 32, j * 128);
      }
    }
  } else {
    const int wg = warp >> 2, w4 = warp & 3, tid = threadIdx.x & 127;
    const float c = 0.17677669529663687f * 1.4426950408889634f;
    mbar_wait(qbar, 0);
    const uint64_t dq = make_desc(sQ + wg * 4096, 16, 512, 2);
    float oacc[16];
#pragma unroll
    for (int i = 0; i < 16; i++) oacc[i] = 0.f;
    float m0 = -INFINITY, m1 = -INFINITY, l0 = 0.f, l1 = 0.f;
    for (int j = 0; j < S_LEN / 128; j++) {
      const int s = j % AT_STAGES; const uint32_t ph = (j / AT_STAGES) & 1;
      mbar_wait(full(s), ph);
      float sacc[64];
      const uint64_t dk = make_desc(sK(s), 16, 512, 2);
      wgmma_fence();
      wgmma_ss_n128<0>(sacc, dq, dk, 0);
      wgmma_ss_n128<0>(sacc, dq + 2, dk + 2, 1);
      wgmma_commit();
      wgmma_wait<0>();
      float mx0 = m0, mx1 = m1;
#pragma unroll
      for (int i = 0; i < 16; i++) {
        mx0 = fmaxf(mx0, fmaxf(sacc[4 * i], sacc[4 * i + 1]));
        mx1 = fmaxf(mx1, fmaxf(sacc[4 * i + 2], sacc[4 * i + 3]));
      }
      mx0 = fmaxf(mx0, __shfl_xor_sync(0xffffffffu, mx0, 1));
      mx0 = fmaxf(mx0, __shfl_xor_sync(0xffffffffu, mx0, 2));
      mx1 = fmaxf(mx1, __shfl_xor_sync(0xffffffffu, mx1, 1));
      mx1 = fmaxf(mx1, __shfl_xor_sync(0xffffffffu, mx1, 2));
      const float a0 = ex2((m0 - mx0) * c), a1 = ex2((m1 - mx1) * c);
      m0 = mx0; m1 = mx1;
      const float nm0 = -mx0 * c, nm1 = -mx1 * c;
      l0 *= a0; l1 *= a1;
#pragma unroll
      for (int i = 0; i < 4; i++) {
        oacc[4 * i] *= a0; oacc[4 * i + 1] *= a0; oacc[4 * i + 2] *= a1; oacc[4 * i + 3] *= a1;
      }
      uint32_t p[32];
#pragma unroll
      for (int i = 0; i < 16; i++) {
        float p0 = ex2(fmaf(sacc[4 * i], c, nm0)), p1 = ex2(fmaf(sacc[4 * i + 1], c, nm0));
        float p2 = ex2(fmaf(sacc[4 * i + 2], c, nm1)), p3 = ex2(fmaf(sacc[4 * i + 3], c, nm1));
        l0 += p0 + p1; l1 += p2 + p3;
        p[2 * i] = pack_bf16(p0, p1);
        p[2 * i + 1] = pack_bf16(p2, p3);
      }
      const uint64_t dv = make_desc(sV(s), 512, 512, 2);
      wgmma_fence();
#pragma unroll
      for (int t = 0; t < 8; t++)
        wgmma_rs_n32<1>(oacc, p[4 * t], p[4 * t + 1], p[4 * t + 2], p[4 * t + 3], dv + t * 64, 1);
      wgmma_commit();
      wgmma_wait<0>();
      if (tid == 0) mbar_arrive(empty(s));
    }
    l0 += __shfl_xor_sync(0xffffffffu, l0, 1); l0 += __shfl_xor_sync(0xffffffffu, l0, 2);
    l1 += __shfl_xor_sync(0xffffffffu, l1, 1); l1 += __shfl_xor_sync(0xffffffffu, l1, 2);
    const float r0 = 1.0f / l0, r1 = 1.0f / l1;
    const int row0 = qt * 256 + wg * 64 + w4 * 16 + (lane >> 2);
    bf16* po = g_o + (size_t)row0 * D_MODEL + head * 32 + (lane & 3) * 2;
#pragma unroll
    for (int i = 0; i < 4; i++) {
      *reinterpret_cast<uint32_t*>(po + 8 * i) = pack_bf16(oacc[4 * i] * r0, oacc[4 * i + 1] * r0);
      *reinterpret_cast<uint32_t*>(po + 8 * D_MODEL + 8 * i) = pack_bf16(oacc[4 * i + 2] * r1, oacc[4 * i + 3] * r1);
    }
  }
}

constexpr int G3_STAGES = 6;
constexpr int G3_A_BYTES = 128 * 64 * 2, G3_B_BYTES = 64 * 128 * 2;
constexpr int G3_STAGE_BYTES = G3_A_BYTES + G3_B_BYTES;
constexpr int G3_SMEM = G3_STAGES * G3_STAGE_BYTES + 1024 + 256;
constexpr int G3_KSTEPS = 16 + 56;

__global__ void __cluster_dims__(2, 1, 1) __launch_bounds__(384, 1)
gemm3_kernel(const __grid_constant__ CUtensorMap tmO, const __grid_constant__ CUtensorMap tmH,
             const __grid_constant__ CUtensorMap tmWo, const __grid_constant__ CUtensorMap tmWd,
             const bf16* __restrict__ x, bf16* __restrict__ out) {
  extern __shared__ uint8_t smem_raw[];
  const uint32_t base = (smem_u32(smem_raw) + 1023) & ~1023u;
  const uint32_t sA = base, sB = base + G3_STAGES * G3_A_BYTES;
  const uint32_t bars = sB + G3_STAGES * G3_B_BYTES;
  auto full = [&](int s) { return bars + 8 * s; };
  auto empty = [&](int s) { return bars + 8 * (G3_STAGES + s); };
  const uint32_t rank = cluster_rank();
  const int wg = threadIdx.x >> 7;
  if (threadIdx.x == 0) {
    for (int s = 0; s < G3_STAGES; s++) { mbar_init(full(s), 1); mbar_init(empty(s), 4); }
    asm volatile("fence.mbarrier_init.release.cluster;" ::: "memory");
    asm volatile("fence.proxy.async.shared::cta;" ::: "memory");
  }
  __syncthreads();
  cluster_sync_all();
  const int mp = (blockIdx.x >> 1) & 7, nt = blockIdx.x >> 4;
  const int m0 = (mp * 2 + rank) * 128, n0 = nt * 128;
  if (wg == 0) {
    reg_dec<40>();
    if (threadIdx.x == 0) {
      int s = 0; uint32_t ph = 0;
      for (int k = 0; k < G3_KSTEPS; k++) {
        const bool p1 = k < 16;
        const int kc = (p1 ? k : k - 16) * 64;
        mbar_wait(empty(s), ph ^ 1);
        mbar_expect_tx(full(s), G3_STAGE_BYTES);
        tma_load_2d(sA + s * G3_A_BYTES, p1 ? &tmO : &tmH, full(s), kc, m0);
        tma_load_2d_mc(sB + s * G3_B_BYTES + rank * 8192, p1 ? &tmWo : &tmWd, full(s), n0 + rank * 64, kc, 3);
        if (++s == G3_STAGES) { s = 0; ph ^= 1; }
      }
    }
    __syncwarp();
    cluster_sync_all();
  } else {
    reg_inc<232>();
    const int cw = wg - 1;
    const int tid = threadIdx.x & 127, lane = tid & 31, w4 = tid >> 5;
    float acc[64];
    uint32_t spk[32];
    int s = 0; uint32_t ph = 0; int prev_s = 0;
    for (int k = 0; k < G3_KSTEPS; k++) {
      mbar_wait(full(s), ph);
      wgmma_fence();
      const uint64_t da = make_desc(sA + s * G3_A_BYTES + cw * 8192, 16, 1024, 1);
      const uint64_t db = make_desc(sB + s * G3_B_BYTES, 8192, 1024, 1);
      const bool first = (k == 0) || (k == 16);
#pragma unroll
      for (int kk = 0; kk < 4; kk++) wgmma_ss_n128<1>(acc, da + kk * 2, db + kk * 128, !(first && kk == 0));
      wgmma_commit();
      if (k == 15) {
        wgmma_wait<0>();
        if (tid < 2) { mbar_arrive_cluster(empty(prev_s), tid); mbar_arrive_cluster(empty(s), tid); }
#pragma unroll
        for (int i = 0; i < 32; i++) spk[i] = pack_bf16(acc[2 * i], acc[2 * i + 1]);
      } else if (k > 0 && k != 16) {
        wgmma_wait<1>();
        if (tid < 2) mbar_arrive_cluster(empty(prev_s), tid);
      }
      prev_s = s;
      if (++s == G3_STAGES) { s = 0; ph ^= 1; }
    }
    wgmma_wait<0>();
    if (tid < 2) mbar_arrive_cluster(empty(prev_s), tid);
    const int row0 = m0 + cw * 64 + w4 * 16 + (lane >> 2);
    const size_t off0 = (size_t)row0 * D_MODEL + n0 + (lane & 3) * 2;
#pragma unroll
    for (int j = 0; j < 16; j++) {
#pragma unroll
      for (int hh = 0; hh < 2; hh++) {
        const size_t off = off0 + (size_t)hh * 8 * D_MODEL + 8 * j;
        const uint32_t xv = *reinterpret_cast<const uint32_t*>(x + off);
        const uint32_t sv = spk[2 * j + hh];
        float r[2];
#pragma unroll
        for (int e = 0; e < 2; e++) {
          const float y = bf16_round(acc[4 * j + 2 * hh + e]);
          const float g = bf16_round(y * rcp(1.0f + ex2(-y * 1.4426950408889634f)));
          const float sf = __uint_as_float(e ? (sv & 0xffff0000u) : (sv << 16));
          const float xf = __uint_as_float(e ? (xv & 0xffff0000u) : (xv << 16));
          r[e] = xf + bf16_round(sf * g);
        }
        *reinterpret_cast<uint32_t*>(out + off) = pack_bf16(r[0], r[1]);
      }
    }
    cluster_sync_all();
  }
}

typedef CUresult (*PFN_encodeTiled_t)(CUtensorMap*, CUtensorMapDataType, cuuint32_t, void*, const cuuint64_t*,
                                      const cuuint64_t*, const cuuint32_t*, const cuuint32_t*, CUtensorMapInterleave,
                                      CUtensorMapSwizzle, CUtensorMapL2promotion, CUtensorMapFloatOOBfill);

static CUtensorMap make_map(PFN_encodeTiled_t fn, const void* ptr, uint64_t rows, uint64_t cols, uint32_t box_cols,
                            uint32_t box_rows, CUtensorMapSwizzle swz) {
  CUtensorMap m;
  cuuint64_t dims[2] = {cols, rows};
  cuuint64_t strides[1] = {cols * 2};
  cuuint32_t box[2] = {box_cols, box_rows};
  cuuint32_t es[2] = {1, 1};
  fn(&m, CU_TENSOR_MAP_DATA_TYPE_BFLOAT16, 2, const_cast<void*>(ptr), dims, strides, box, es,
     CU_TENSOR_MAP_INTERLEAVE_NONE, swz, CU_TENSOR_MAP_L2_PROMOTION_L2_128B, CU_TENSOR_MAP_FLOAT_OOB_FILL_NONE);
  return m;
}

extern "C" void kernel_launch(void* const* d_in, const int* in_sizes, int n_in, void* d_out, int out_size) {
  const bf16* x = (const bf16*)d_in[0];
  const bf16* wqkv = (const bf16*)d_in[1];
  const bf16* wo = (const bf16*)d_in[2];
  const bf16* wg = (const bf16*)d_in[4];
  const bf16* wu = (const bf16*)d_in[5];
  const bf16* wd = (const bf16*)d_in[6];
  bf16* out = (bf16*)d_out;

  static PFN_encodeTiled_t enc = nullptr;
  if (!enc) {
    void* fp = nullptr;
    cudaDriverEntryPointQueryResult qr;
    cudaGetDriverEntryPoint("cuTensorMapEncodeTiled", &fp, cudaEnableDefault, &qr);
    enc = (PFN_encodeTiled_t)fp;
  }
  void *p_xn, *p_qkv, *p_h, *p_o;
  cudaGetSymbolAddress(&p_xn, g_xn);
  cudaGetSymbolAddress(&p_qkv, g_qkv);
  cudaGetSymbolAddress(&p_h, g_h);
  cudaGetSymbolAddress(&p_o, g_o);

  const CUtensorMap tmXn = make_map(enc, p_xn, S_LEN, D_MODEL, 64, 128, CU_TENSOR_MAP_SWIZZLE_128B);
  const CUtensorMap tmWqkv = make_map(enc, wqkv, D_MODEL, 3 * D_MODEL, 64, 64, CU_TENSOR_MAP_SWIZZLE_128B);
  const CUtensorMap tmWg = make_map(enc, wg, D_MODEL, F_DIM, 64, 64, CU_TENSOR_MAP_SWIZZLE_128B);
  const CUtensorMap tmWu = make_map(enc, wu, D_MODEL, F_DIM, 64, 64, CU_TENSOR_MAP_SWIZZLE_128B);
  const CUtensorMap tmQKV = make_map(enc, p_qkv, S_LEN, 3 * D_MODEL, 32, 128, CU_TENSOR_MAP_SWIZZLE_64B);
  const CUtensorMap tmO = make_map(enc, p_o, S_LEN, D_MODEL, 64, 128, CU_TENSOR_MAP_SWIZZLE_128B);
  const CUtensorMap tmH = make_map(enc, p_h, S_LEN, F_DIM, 64, 128, CU_TENSOR_MAP_SWIZZLE_128B);
  const CUtensorMap tmWo = make_map(enc, wo, D_MODEL, D_MODEL, 64, 64, CU_TENSOR_MAP_SWIZZLE_128B);
  const CUtensorMap tmWd = make_map(enc, wd, F_DIM, D_MODEL, 64, 64, CU_TENSOR_MAP_SWIZZLE_128B);

  cudaFuncSetAttribute(gemm1_kernel, cudaFuncAttributeMaxDynamicSharedMemorySize, G1_SMEM);
  cudaFuncSetAttribute(attn_kernel, cudaFuncAttributeMaxDynamicSharedMemorySize, AT_SMEM);
  cudaFuncSetAttribute(gemm3_kernel, cudaFuncAttributeMaxDynamicSharedMemorySize, G3_SMEM);

  ln_kernel<<<S_LEN / 8, 256>>>(x);
  gemm1_kernel<<<132, 384, G1_SMEM>>>(tmXn, tmWqkv, tmWg, tmWu);
  attn_kernel<<<256, 544, AT_SMEM>>>(tmQKV);
  gemm3_kernel<<<128, 384, G3_SMEM>>>(tmO, tmH, tmWo, tmWd, x, out);
}
```

```cpp
#include <cuda_runtime.h>
#include <cuda_bf16.h>
#include <cuda.h>
#include <stdint.h>

#define DEV __device__ __forceinline__
typedef __nv_bfloat16 bf16;

constexpr int S_LEN = 2048, D_MODEL = 1024, F_DIM = 3584, N_HEADS = 32, D_HEAD = 32;

__device__ __align__(1024) bf16 g_xn[S_LEN * D_MODEL];
__device__ __align__(1024) bf16 g_qkv[S_LEN * 3 * D_MODEL];
__device__ __align__(1024) bf16 g_h[S_LEN * F_DIM];
__device__ __align__(1024) bf16 g_o[S_LEN * D_MODEL];
#define TS(i)

DEV uint32_t smem_u32(const void* p) { return (uint32_t)__cvta_generic_to_shared(p); }
DEV void mbar_init(uint32_t bar, uint32_t count) {
  asm volatile("mbarrier.init.shared::cta.b64 [%0], %1;" ::"r"(bar), "r"(count) : "memory");
}
DEV void mbar_expect_tx(uint32_t bar, uint32_t bytes) {
  asm volatile("mbarrier.arrive.expect_tx.shared::cta.b64 _, [%0], %1;" ::"r"(bar), "r"(bytes) : "memory");
}
DEV void mbar_arrive(uint32_t bar) { asm volatile("mbarrier.arrive.shared::cta.b64 _, [%0];" ::"r"(bar) : "memory"); }
DEV void mbar_arrive_cluster(uint32_t bar, uint32_t cta) {
  asm volatile(
      "{\n.reg .b32 ra;\nmapa.shared::cluster.u32 ra, %0, %1;\n"
      "mbarrier.arrive.shared::cluster.b64 _, [ra];\n}\n" ::"r"(bar), "r"(cta) : "memory");
}
DEV void mbar_wait(uint32_t bar, uint32_t parity) {
  uint32_t ok, spins = 0;
  do {
    asm volatile(
        "{\n.reg .pred p;\nmbarrier.try_wait.parity.shared::cta.b64 p, [%1], %2;\nselp.u32 %0, 1, 0, p;\n}\n"
        : "=r"(ok) : "r"(bar), "r"(parity) : "memory");
    if (++spins > (1u << 24)) asm volatile("trap;");
  } while (!ok);
}
DEV void cluster_sync_all() {
  asm volatile("barrier.cluster.arrive.release.aligned;\nbarrier.cluster.wait.acquire.aligned;\n" ::: "memory");
}
DEV uint32_t cluster_rank() { uint32_t r; asm volatile("mov.u32 %0, %%cluster_ctarank;" : "=r"(r)); return r; }
DEV void tma_load_2d(uint32_t dst, const CUtensorMap* map, uint32_t bar, int c0, int c1) {
  asm volatile(
      "cp.async.bulk.tensor.2d.shared::cluster.global.mbarrier::complete_tx::bytes [%0], [%1, {%3, %4}], [%2];"
      ::"r"(dst), "l"(map), "r"(bar), "r"(c0), "r"(c1) : "memory");
}
DEV void tma_load_2d_mc(uint32_t dst, const CUtensorMap* map, uint32_t bar, int c0, int c1, uint16_t mask) {
  asm volatile(
      "cp.async.bulk.tensor.2d.shared::cluster.global.mbarrier::complete_tx::bytes.multicast::cluster "
      "[%0], [%1, {%3, %4}], [%2], %5;"
      ::"r"(dst), "l"(map), "r"(bar), "r"(c0), "r"(c1), "h"(mask) : "memory");
}
DEV void prefetch_tmap(const CUtensorMap* map) {
  asm volatile("prefetch.tensormap [%0];" ::"l"(map) : "memory");
}
DEV void wgmma_fence() { asm volatile("wgmma.fence.sync.aligned;" ::: "memory"); }
DEV void wgmma_commit() { asm volatile("wgmma.commit_group.sync.aligned;" ::: "memory"); }
template <int N> DEV void wgmma_wait() { asm volatile("wgmma.wait_group.sync.aligned %0;" ::"n"(N) : "memory"); }
template <int R> DEV void reg_inc() { asm volatile("setmaxnreg.inc.sync.aligned.u32 %0;" ::"n"(R)); }
template <int R> DEV void reg_dec() { asm volatile("setmaxnreg.dec.sync.aligned.u32 %0;" ::"n"(R)); }

DEV uint64_t make_desc(uint32_t addr, uint32_t lbo, uint32_t sbo, uint32_t swz) {
  return (uint64_t)((addr & 0x3FFFF) >> 4) | ((uint64_t)(lbo >> 4) << 16) | ((uint64_t)(sbo >> 4) << 32) |
         ((uint64_t)swz << 62);
}
DEV float ex2(float x) { float y; asm("ex2.approx.ftz.f32 %0, %1;" : "=f"(y) : "f"(x)); return y; }
DEV float rcp(float x) { float y; asm("rcp.approx.ftz.f32 %0, %1;" : "=f"(y) : "f"(x)); return y; }
DEV uint32_t pack_bf16(float lo, float hi) {
  uint32_t r; asm("cvt.rn.bf16x2.f32 %0, %1, %2;" : "=r"(r) : "f"(hi), "f"(lo)); return r;
}
DEV float bf16_round(float x) { return __bfloat162float(__float2bfloat16_rn(x)); }
DEV void round_pair(float& a, float& b) {
  const uint32_t w = pack_bf16(a, b);
  a = __uint_as_float(w << 16); b = __uint_as_float(w & 0xffff0000u);
}

template<int TB>
DEV void wgmma_ss_n256(float (&d)[128], uint64_t da, uint64_t db, int sd) {
  asm volatile("{\n.reg .pred p;\nsetp.ne.b32 p, %130, 0;\n"
    "wgmma.mma_async.sync.aligned.m64n256k16.f32.bf16.bf16 "
    "{%0, %1, %2, %3, %4, %5, %6, %7, %8, %9, %10, %11, %12, %13, %14, %15, %16, %17, %18, %19, %20, %21, %22, %23, %24, %25, %26, %27, %28, %29, %30, %31, %32, %33, %34, %35, %36, %37, %38, %39, %40, %41, %42, %43, %44, %45, %46, %47, %48, %49, %50, %51, %52, %53, %54, %55, %56, %57, %58, %59, %60, %61, %62, %63, %64, %65, %66, %67, %68, %69, %70, %71, %72, %73, %74, %75, %76, %77, %78, %79, %80, %81, %82, %83, %84, %85, %86, %87, %88, %89, %90, %91, %92, %93, %94, %95, %96, %97, %98, %99, %100, %101, %102, %103, %104, %105, %106, %107, %108, %109, %110, %111, %112, %113, %114, %115, %116, %117, %118, %119, %120, %121, %122, %123, %124, %125, %126, %127}, %128, %129, p, 1, 1, 0, %131;\n}\n"
    : "+f"(d[0]), "+f"(d[1]), "+f"(d[2]), "+f"(d[3]), "+f"(d[4]), "+f"(d[5]), "+f"(d[6]), "+f"(d[7]), "+f"(d[8]), "+f"(d[9]), "+f"(d[10]), "+f"(d[11]), "+f"(d[12]), "+f"(d[13]), "+f"(d[14]), "+f"(d[15]), "+f"(d[16]), "+f"(d[17]), "+f"(d[18]), "+f"(d[19]), "+f"(d[20]), "+f"(d[21]), "+f"(d[22]), "+f"(d[23]), "+f"(d[24]), "+f"(d[25]), "+f"(d[26]), "+f"(d[27]), "+f"(d[28]), "+f"(d[29]), "+f"(d[30]), "+f"(d[31]), "+f"(d[32]), "+f"(d[33]), "+f"(d[34]), "+f"(d[35]), "+f"(d[36]), "+f"(d[37]), "+f"(d[38]), "+f"(d[39]), "+f"(d[40]), "+f"(d[41]), "+f"(d[42]), "+f"(d[43]), "+f"(d[44]), "+f"(d[45]), "+f"(d[46]), "+f"(d[47]), "+f"(d[48]), "+f"(d[49]), "+f"(d[50]), "+f"(d[51]), "+f"(d[52]), "+f"(d[53]), "+f"(d[54]), "+f"(d[55]), "+f"(d[56]), "+f"(d[57]), "+f"(d[58]), "+f"(d[59]), "+f"(d[60]), "+f"(d[61]), "+f"(d[62]), "+f"(d[63]), "+f"(d[64]), "+f"(d[65]), "+f"(d[66]), "+f"(d[67]), "+f"(d[68]), "+f"(d[69]), "+f"(d[70]), "+f"(d[71]), "+f"(d[72]), "+f"(d[73]), "+f"(d[74]), "+f"(d[75]), "+f"(d[76]), "+f"(d[77]), "+f"(d[78]), "+f"(d[79]), "+f"(d[80]), "+f"(d[81]), "+f"(d[82]), "+f"(d[83]), "+f"(d[84]), "+f"(d[85]), "+f"(d[86]), "+f"(d[87]), "+f"(d[88]), "+f"(d[89]), "+f"(d[90]), "+f"(d[91]), "+f"(d[92]), "+f"(d[93]), "+f"(d[94]), "+f"(d[95]), "+f"(d[96]), "+f"(d[97]), "+f"(d[98]), "+f"(d[99]), "+f"(d[100]), "+f"(d[101]), "+f"(d[102]), "+f"(d[103]), "+f"(d[104]), "+f"(d[105]), "+f"(d[106]), "+f"(d[107]), "+f"(d[108]), "+f"(d[109]), "+f"(d[110]), "+f"(d[111]), "+f"(d[112]), "+f"(d[113]), "+f"(d[114]), "+f"(d[115]), "+f"(d[116]), "+f"(d[117]), "+f"(d[118]), "+f"(d[119]), "+f"(d[120]), "+f"(d[121]), "+f"(d[122]), "+f"(d[123]), "+f"(d[124]), "+f"(d[125]), "+f"(d[126]), "+f"(d[127])
    : "l"(da), "l"(db), "r"(sd), "n"(TB));
}
template<int TB>
DEV void wgmma_ss_n128(float (&d)[64], uint64_t da, uint64_t db, int sd) {
  asm volatile("{\n.reg .pred p;\nsetp.ne.b32 p, %66, 0;\n"
    "wgmma.mma_async.sync.aligned.m64n128k16.f32.bf16.bf16 "
    "{%0, %1, %2, %3, %4, %5, %6, %7, %8, %9, %10, %11, %12, %13, %14, %15, %16, %17, %18, %19, %20, %21, %22, %23, %24, %25, %26, %27, %28, %29, %30, %31, %32, %33, %34, %35, %36, %37, %38, %39, %40, %41, %42, %43, %44, %45, %46, %47, %48, %49, %50, %51, %52, %53, %54, %55, %56, %57, %58, %59, %60, %61, %62, %63}, %64, %65, p, 1, 1, 0, %67;\n}\n"
    : "+f"(d[0]), "+f"(d[1]), "+f"(d[2]), "+f"(d[3]), "+f"(d[4]), "+f"(d[5]), "+f"(d[6]), "+f"(d[7]), "+f"(d[8]), "+f"(d[9]), "+f"(d[10]), "+f"(d[11]), "+f"(d[12]), "+f"(d[13]), "+f"(d[14]), "+f"(d[15]), "+f"(d[16]), "+f"(d[17]), "+f"(d[18]), "+f"(d[19]), "+f"(d[20]), "+f"(d[21]), "+f"(d[22]), "+f"(d[23]), "+f"(d[24]), "+f"(d[25]), "+f"(d[26]), "+f"(d[27]), "+f"(d[28]), "+f"(d[29]), "+f"(d[30]), "+f"(d[31]), "+f"(d[32]), "+f"(d[33]), "+f"(d[34]), "+f"(d[35]), "+f"(d[36]), "+f"(d[37]), "+f"(d[38]), "+f"(d[39]), "+f"(d[40]), "+f"(d[41]), "+f"(d[42]), "+f"(d[43]), "+f"(d[44]), "+f"(d[45]), "+f"(d[46]), "+f"(d[47]), "+f"(d[48]), "+f"(d[49]), "+f"(d[50]), "+f"(d[51]), "+f"(d[52]), "+f"(d[53]), "+f"(d[54]), "+f"(d[55]), "+f"(d[56]), "+f"(d[57]), "+f"(d[58]), "+f"(d[59]), "+f"(d[60]), "+f"(d[61]), "+f"(d[62]), "+f"(d[63])
    : "l"(da), "l"(db), "r"(sd), "n"(TB));
}
template<int TB>
DEV void wgmma_ss_n64(float (&d)[32], uint64_t da, uint64_t db, int sd) {
  asm volatile("{\n.reg .pred p;\nsetp.ne.b32 p, %34, 0;\n"
    "wgmma.mma_async.sync.aligned.m64n64k16.f32.bf16.bf16 "
    "{%0, %1, %2, %3, %4, %5, %6, %7, %8, %9, %10, %11, %12, %13, %14, %15, %16, %17, %18, %19, %20, %21, %22, %23, %24, %25, %26, %27, %28, %29, %30, %31}, %32, %33, p, 1, 1, 0, %35;\n}\n"
    : "+f"(d[0]), "+f"(d[1]), "+f"(d[2]), "+f"(d[3]), "+f"(d[4]), "+f"(d[5]), "+f"(d[6]), "+f"(d[7]), "+f"(d[8]), "+f"(d[9]), "+f"(d[10]), "+f"(d[11]), "+f"(d[12]), "+f"(d[13]), "+f"(d[14]), "+f"(d[15]), "+f"(d[16]), "+f"(d[17]), "+f"(d[18]), "+f"(d[19]), "+f"(d[20]), "+f"(d[21]), "+f"(d[22]), "+f"(d[23]), "+f"(d[24]), "+f"(d[25]), "+f"(d[26]), "+f"(d[27]), "+f"(d[28]), "+f"(d[29]), "+f"(d[30]), "+f"(d[31])
    : "l"(da), "l"(db), "r"(sd), "n"(TB));
}
template<int TB>
DEV void wgmma_rs_n32(float (&d)[16], uint32_t a0, uint32_t a1, uint32_t a2, uint32_t a3, uint64_t db, int sd) {
  asm volatile("{\n.reg .pred p;\nsetp.ne.b32 p, %21, 0;\n"
    "wgmma.mma_async.sync.aligned.m64n32k16.f32.bf16.bf16 "
    "{%0, %1, %2, %3, %4, %5, %6, %7, %8, %9, %10, %11, %12, %13, %14, %15}, {%16, %17, %18, %19}, %20, p, 1, 1, %22;\n}\n"
    : "+f"(d[0]), "+f"(d[1]), "+f"(d[2]), "+f"(d[3]), "+f"(d[4]), "+f"(d[5]), "+f"(d[6]), "+f"(d[7]), "+f"(d[8]), "+f"(d[9]), "+f"(d[10]), "+f"(d[11]), "+f"(d[12]), "+f"(d[13]), "+f"(d[14]), "+f"(d[15])
    : "r"(a0), "r"(a1), "r"(a2), "r"(a3), "l"(db), "r"(sd), "n"(TB));
}

__global__ void __launch_bounds__(256) ln_kernel(const bf16* __restrict__ x) {
  const int row = blockIdx.x * 8 + (threadIdx.x >> 5);
  const int lane = threadIdx.x & 31;
  const uint4* src = reinterpret_cast<const uint4*>(x + (size_t)row * D_MODEL);
  float f[32];
#pragma unroll
  for (int i = 0; i < 4; i++) {
    uint4 v = __ldg(src + lane + 32 * i);
    const uint32_t w[4] = {v.x, v.y, v.z, v.w};
#pragma unroll
    for (int j = 0; j < 4; j++) {
      f[i * 8 + 2 * j] = __uint_as_float(w[j] << 16);
      f[i * 8 + 2 * j + 1] = __uint_as_float(w[j] & 0xffff0000u);
    }
  }
  float sum = 0.f;
#pragma unroll
  for (int i = 0; i < 32; i++) sum += f[i];
#pragma unroll
  for (int o = 16; o; o >>= 1) sum += __shfl_xor_sync(0xffffffffu, sum, o);
  const float mean = sum * (1.0f / D_MODEL);
  float sq = 0.f;
#pragma unroll
  for (int i = 0; i < 32; i++) { float d = f[i] - mean; sq += d * d; }
#pragma unroll
  for (int o = 16; o; o >>= 1) sq += __shfl_xor_sync(0xffffffffu, sq, o);
  const float m_b = bf16_round(mean);
  const float v_b = bf16_round(sq * (1.0f / D_MODEL));
  const float den = bf16_round(sqrtf(bf16_round(v_b + 1e-5f)));
  uint4* dst = reinterpret_cast<uint4*>(g_xn + (size_t)row * D_MODEL);
#pragma unroll
  for (int i = 0; i < 4; i++) {
    uint32_t w[4];
#pragma unroll
    for (int j = 0; j < 4; j++) {
      float a = bf16_round(f[i * 8 + 2 * j] - m_b) / den;
      float b = bf16_round(f[i * 8 + 2 * j + 1] - m_b) / den;
      w[j] = pack_bf16(a, b);
    }
    dst[lane + 32 * i] = make_uint4(w[0], w[1], w[2], w[3]);
  }
}

constexpr int G1_STAGES = 4;
constexpr int G1_A_BYTES = 128 * 64 * 2, G1_B_BYTES = 64 * 256 * 2;
constexpr int G1_STAGE_BYTES = G1_A_BYTES + G1_B_BYTES;
constexpr int G1_SMEM = G1_STAGES * G1_STAGE_BYTES + 32768 + 1024 + 256;
constexpr int G1_NUM_CT = 8 * 40;

DEV void quad_transpose(uint32_t (&v)[4], int q) {
  const bool o1 = q & 1, o2 = q & 2;
  uint32_t t0 = o1 ? v[0] : v[1], t1 = o1 ? v[2] : v[3];
  t0 = __shfl_xor_sync(0xffffffffu, t0, 1); t1 = __shfl_xor_sync(0xffffffffu, t1, 1);
  if (o1) { v[0] = t0; v[2] = t1; } else { v[1] = t0; v[3] = t1; }
  t0 = o2 ? v[0] : v[2]; t1 = o2 ? v[1] : v[3];
  t0 = __shfl_xor_sync(0xffffffffu, t0, 2); t1 = __shfl_xor_sync(0xffffffffu, t1, 2);
  if (o2) { v[0] = t0; v[1] = t1; } else { v[2] = t0; v[3] = t1; }
}

DEV float gelu_tanh(float x) {
  const float c = 2.0f * 0.7978845608028654f * 1.4426950408889634f;
  float t = x * x;
  float u = fmaf(t, 0.044715f, 1.0f);
  float z = x * u * c;
  float e = ex2(-z);
  return x * rcp(1.0f + e);
}

__global__ void __cluster_dims__(2, 1, 1) __launch_bounds__(384, 1)
gemm1_kernel(const __grid_constant__ CUtensorMap tmA, const __grid_constant__ CUtensorMap tmQKV,
             const __grid_constant__ CUtensorMap tmG, const __grid_constant__ CUtensorMap tmU) {
  extern __shared__ uint8_t smem_raw[];
  const uint32_t base = (smem_u32(smem_raw) + 1023) & ~1023u;
  const uint32_t sA = base, sB = base + G1_STAGES * G1_A_BYTES;
  const uint32_t bars = sB + G1_STAGES * G1_B_BYTES + 32768;
  auto full = [&](int s) { return bars + 8 * s; };
  auto empty = [&](int s) { return bars + 8 * (G1_STAGES + s); };
  const uint32_t rank = cluster_rank();
  const int wg = threadIdx.x >> 7;
  if (threadIdx.x == 0) {
    for (int s = 0; s < G1_STAGES; s++) { mbar_init(full(s), 1); mbar_init(empty(s), 4); }
    asm volatile("fence.mbarrier_init.release.cluster;" ::: "memory");
    asm volatile("fence.proxy.async.shared::cta;" ::: "memory");
  }
  __syncthreads();
  cluster_sync_all();
  const int n_clusters = gridDim.x >> 1, cluster_id = blockIdx.x >> 1;

  if (wg == 0) {
    reg_dec<24>();
    if (threadIdx.x == 0) {
      int s = 0; uint32_t ph = 0;
      for (int ct = cluster_id; ct < G1_NUM_CT; ct += n_clusters) {
        const int mp = ct & 7, nt = ct >> 3;
        const int m0 = (mp * 2 + rank) * 128;
        const CUtensorMap* bmap; int bcol;
        if (nt < 12) { bmap = &tmQKV; bcol = nt * 256 + rank * 128; }
        else { bmap = rank ? &tmU : &tmG; bcol = (nt - 12) * 128; }
        for (int k = 0; k < 16; k++) {
          mbar_wait(empty(s), ph ^ 1);
          mbar_expect_tx(full(s), G1_STAGE_BYTES);
          tma_load_2d(sA + s * G1_A_BYTES, &tmA, full(s), k * 64, m0);
          tma_load_2d_mc(sB + s * G1_B_BYTES + (2 * rank) * 8192, bmap, full(s), bcol, k * 64, 3);
          tma_load_2d_mc(sB + s * G1_B_BYTES + (2 * rank + 1) * 8192, bmap, full(s), bcol + 64, k * 64, 3);
          if (++s == G1_STAGES) { s = 0; ph ^= 1; }
        }
      }
    }
    __syncwarp();
    cluster_sync_all();
  } else {
    reg_inc<240>();
    const int cw = wg - 1;
    const int tid = threadIdx.x & 127, lane = tid & 31, w4 = tid >> 5;
    float acc[128];
    uint32_t pr[32];
    const uint32_t sPark = sB + G1_STAGES * G1_B_BYTES + (threadIdx.x - 128) * 16;
    int pend = 0;
    bf16* pptr = nullptr;
    const int q = lane & 3;
    auto slot = [](int g, int hf) { return (((g & 1) | ((g >> 2) << 1)) * 2 + hf); };
    auto chunk_qkv = [&](int c) {
      const int gp = c >> 1, hf = c & 1;
      const int g = gp < 2 ? gp : (gp < 4 ? gp + 2 : (gp < 6 ? gp - 2 : gp));
      uint32_t a[4];
      if ((g & 2) == 0) {
#pragma unroll
        for (int i = 0; i < 4; i++) a[i] = pr[4 * slot(g, hf) + i];
      } else {
        asm volatile("ld.shared.v4.u32 {%0,%1,%2,%3}, [%4];"
                     : "=r"(a[0]), "=r"(a[1]), "=r"(a[2]), "=r"(a[3]) : "r"(sPark + slot(g, hf) * 4096));
      }
      quad_transpose(a, q);
      *reinterpret_cast<uint4*>(pptr + (size_t)g * S_LEN * 32 + hf * 8 * 32) = make_uint4(a[0], a[1], a[2], a[3]);
    };
    uint32_t ha[4];
    auto chunk_geglu = [&](int c2) {
      const int c = c2 >> 1, part = c2 & 1;
      const int g = c >> 1, hf = c & 1;
      uint32_t gw[2], uw[2];
      if ((g & 2) == 0) {
#pragma unroll
        for (int i = 0; i < 2; i++) { gw[i] = pr[4 * slot(g, hf) + 2 * part + i]; uw[i] = pr[4 * slot(g + 4, hf) + 2 * part + i]; }
      } else {
        asm volatile("ld.shared.v2.u32 {%0,%1}, [%2];" : "=r"(gw[0]), "=r"(gw[1]) : "r"(sPark + slot(g, hf) * 4096 + part * 8));
        asm volatile("ld.shared.v2.u32 {%0,%1}, [%2];" : "=r"(uw[0]), "=r"(uw[1]) : "r"(sPark + slot(g + 4, hf) * 4096 + part * 8));
      }
#pragma unroll
      for (int i = 0; i < 2; i++) {
        float g0 = gelu_tanh(__uint_as_float(gw[i] << 16)), g1 = gelu_tanh(__uint_as_float(gw[i] & 0xffff0000u));
        round_pair(g0, g1);
        ha[2 * part + i] = pack_bf16(g0 * __uint_as_float(uw[i] << 16), g1 * __uint_as_float(uw[i] & 0xffff0000u));
      }
      if (part) {
        quad_transpose(ha, q);
        *reinterpret_cast<uint4*>(pptr + g * 32 + hf * 8 * F_DIM) = make_uint4(ha[0], ha[1], ha[2], ha[3]);
      }
    };
    static_assert(16 % G1_STAGES == 0 && ((16 / G1_STAGES) & 1) == 0, "static stage schedule");
    const uint64_t da0 = make_desc(sA + cw * 8192, 16, 1024, 1);
    const uint64_t db0 = make_desc(sB, 8192, 1024, 1);
    for (int ct = cluster_id; ct < G1_NUM_CT; ct += n_clusters) {
      TS(0);
#pragma unroll
      for (int k = 0; k < 16; k++) {
        const int st = k % G1_STAGES;
        mbar_wait(full(st), (k / G1_STAGES) & 1);
        if (k == 0) TS(1);
        wgmma_fence();
#pragma unroll
        for (int kk = 0; kk < 4; kk++)
          wgmma_ss_n256<1>(acc, da0 + (st * G1_A_BYTES >> 4) + kk * 2, db0 + (st * G1_B_BYTES >> 4) + kk * 128, (k | kk) != 0);
        wgmma_commit();
        if (k > 0) {
          wgmma_wait<1>();
          if (tid < 2) mbar_arrive_cluster(empty((k - 1) % G1_STAGES), tid);
        }
        if (pend == 1) chunk_qkv(k);
        else if (pend == 2) chunk_geglu(k);
      }
      wgmma_wait<0>();
      if (tid < 2) mbar_arrive_cluster(empty(15 % G1_STAGES), tid);
      TS(2);
#pragma unroll
      for (int g = 0; g < 8; g++) {
#pragma unroll
        for (int hf = 0; hf < 2; hf++) {
          uint32_t v[4];
#pragma unroll
          for (int i = 0; i < 4; i++) v[i] = pack_bf16(acc[16 * g + 4 * i + 2 * hf], acc[16 * g + 4 * i + 2 * hf + 1]);
          if ((g & 2) == 0) {
#pragma unroll
            for (int i = 0; i < 4; i++) pr[4 * slot(g, hf) + i] = v[i];
          } else {
            asm volatile("st.shared.v4.u32 [%0], {%1,%2,%3,%4};" ::"r"(sPark + slot(g, hf) * 4096), "r"(v[0]), "r"(v[1]),
                         "r"(v[2]), "r"(v[3]) : "memory");
          }
        }
      }
      const int mp = ct & 7, nt = ct >> 3;
      const int row0 = (mp * 2 + rank) * 128 + cw * 64 + w4 * 16 + (lane >> 2);
      if (nt < 12) { pend = 1; pptr = g_qkv + ((size_t)(nt * 8) * S_LEN + row0) * 32 + q * 8; }
      else { pend = 2; pptr = g_h + (size_t)row0 * F_DIM + (nt - 12) * 128 + q * 8; }
      TS(3);
    }
    if (pend == 1) {
#pragma unroll
      for (int c = 0; c < 16; c++) chunk_qkv(c);
    } else if (pend == 2) {
#pragma unroll
      for (int c = 0; c < 16; c++) chunk_geglu(c);
    }
    cluster_sync_all();
  }
}

constexpr int AT_STAGES = 8;
constexpr int AT_SMEM = 16384 + AT_STAGES * 16384 + 1024 + 256;

__global__ void __launch_bounds__(512, 1) attn_kernel(const __grid_constant__ CUtensorMap tmQKV) {
  extern __shared__ uint8_t smem_raw[];
  const uint32_t base = (smem_u32(smem_raw) + 1023) & ~1023u;
  const uint32_t sQ = base;
  auto sK = [&](int s) { return base + 16384 + s * 16384; };
  auto sV = [&](int s) { return base + 16384 + s * 16384 + 8192; };
  const uint32_t bars = base + 16384 + AT_STAGES * 16384;
  auto full = [&](int s) { return bars + 8 * s; };
  auto empty = [&](int s) { return bars + 8 * (AT_STAGES + s); };
  const uint32_t qbar = bars + 8 * 2 * AT_STAGES;
  const int head = blockIdx.x >> 3, qt = blockIdx.x & 7;
  const int warp = threadIdx.x >> 5, lane = threadIdx.x & 31;
  if (threadIdx.x == 0) {
    for (int s = 0; s < AT_STAGES; s++) { mbar_init(full(s), 1); mbar_init(empty(s), 4); }
    mbar_init(qbar, 1);
    asm volatile("fence.proxy.async.shared::cta;" ::: "memory");
    mbar_expect_tx(qbar, 16384);
    tma_load_2d(sQ, &tmQKV, qbar, 0, head * S_LEN + qt * 256);
    tma_load_2d(sQ + 8192, &tmQKV, qbar, 0, head * S_LEN + qt * 256 + 128);
    for (int j = 0; j < AT_STAGES; j++) {
      mbar_expect_tx(full(j), 16384);
      tma_load_2d(sK(j), &tmQKV, full(j), 0, (N_HEADS + head) * S_LEN + j * 128);
      tma_load_2d(sV(j), &tmQKV, full(j), 0, (2 * N_HEADS + head) * S_LEN + j * 128);
    }
  }
  __syncthreads();
  {
    const int wg = warp >> 2, w4 = warp & 3, tid = threadIdx.x & 127;
    const float c = 0.17677669529663687f * 1.4426950408889634f;
    mbar_wait(qbar, 0);
    const uint64_t dq = make_desc(sQ + wg * 4096, 16, 512, 2);
    float oacc[16];
#pragma unroll
    for (int i = 0; i < 16; i++) oacc[i] = 0.f;
    float m0 = -INFINITY, m1 = -INFINITY, l0 = 0.f, l1 = 0.f;
    float sa[32], sb[32];
    auto issue_qk = [&](float (&sc)[32], int j) {
      const uint64_t dk = make_desc(sK((j >> 1) % AT_STAGES) + (j & 1) * 4096, 16, 512, 2);
      wgmma_fence();
      wgmma_ss_n64<0>(sc, dq, dk, 0);
      wgmma_ss_n64<0>(sc, dq + 2, dk + 2, 1);
      wgmma_commit();
    };
    auto step = [&](float (&sc)[32], float (&sn)[32], int j) {
      if (j + 1 < 2 * (S_LEN / 128)) {
        if (((j + 1) & 1) == 0) mbar_wait(full(((j + 1) >> 1) % AT_STAGES), (((j + 1) >> 1) / AT_STAGES) & 1);
        issue_qk(sn, j + 1);
        wgmma_wait<1>();
      } else {
        wgmma_wait<0>();
      }
      if ((j & 1) == 0 && j >= 2 && tid == 0) {
        const int jb = (j >> 1) - 1;
        mbar_arrive(empty(jb % AT_STAGES));
        const int jr = jb - 1;
        if (jr >= 0 && jr + AT_STAGES < S_LEN / 128 && (jr & 3) == wg) {
          const int sbk = jr % AT_STAGES;
          mbar_wait(empty(sbk), 0);
          mbar_expect_tx(full(sbk), 16384);
          tma_load_2d(sK(sbk), &tmQKV, full(sbk), 0, (N_HEADS + head) * S_LEN + (jr + AT_STAGES) * 128);
          tma_load_2d(sV(sbk), &tmQKV, full(sbk), 0, (2 * N_HEADS + head) * S_LEN + (jr + AT_STAGES) * 128);
        }
      }
      float mx0 = m0, mx1 = m1;
#pragma unroll
      for (int i = 0; i < 8; i++) {
        mx0 = fmaxf(mx0, fmaxf(sc[4 * i], sc[4 * i + 1]));
        mx1 = fmaxf(mx1, fmaxf(sc[4 * i + 2], sc[4 * i + 3]));
      }
      mx0 = fmaxf(mx0, __shfl_xor_sync(0xffffffffu, mx0, 1));
      mx0 = fmaxf(mx0, __shfl_xor_sync(0xffffffffu, mx0, 2));
      mx1 = fmaxf(mx1, __shfl_xor_sync(0xffffffffu, mx1, 1));
      mx1 = fmaxf(mx1, __shfl_xor_sync(0xffffffffu, mx1, 2));
      const float a0 = ex2((m0 - mx0) * c), a1 = ex2((m1 - mx1) * c);
      m0 = mx0; m1 = mx1;
      const float nm0 = -mx0 * c, nm1 = -mx1 * c;
      l0 *= a0; l1 *= a1;
#pragma unroll
      for (int i = 0; i < 4; i++) {
        oacc[4 * i] *= a0; oacc[4 * i + 1] *= a0; oacc[4 * i + 2] *= a1; oacc[4 * i + 3] *= a1;
      }
      uint32_t p[16];
#pragma unroll
      for (int i = 0; i < 8; i++) {
        float p0 = ex2(fmaf(sc[4 * i], c, nm0)), p1 = ex2(fmaf(sc[4 * i + 1], c, nm0));
        float p2 = ex2(fmaf(sc[4 * i + 2], c, nm1)), p3 = ex2(fmaf(sc[4 * i + 3], c, nm1));
        l0 += p0 + p1; l1 += p2 + p3;
        p[2 * i] = pack_bf16(p0, p1);
        p[2 * i + 1] = pack_bf16(p2, p3);
      }
      const uint64_t dv = make_desc(sV((j >> 1) % AT_STAGES) + (j & 1) * 4096, 512, 512, 2);
      wgmma_fence();
#pragma unroll
      for (int t = 0; t < 4; t++)
        wgmma_rs_n32<1>(oacc, p[4 * t], p[4 * t + 1], p[4 * t + 2], p[4 * t + 3], dv + t * 64, 1);
      wgmma_commit();
    };
    mbar_wait(full(0), 0);
    issue_qk(sa, 0);
    for (int j = 0; j < 2 * (S_LEN / 128); j += 2) {
      step(sa, sb, j);
      step(sb, sa, j + 1);
    }
    wgmma_wait<0>();
    l0 += __shfl_xor_sync(0xffffffffu, l0, 1); l0 += __shfl_xor_sync(0xffffffffu, l0, 2);
    l1 += __shfl_xor_sync(0xffffffffu, l1, 1); l1 += __shfl_xor_sync(0xffffffffu, l1, 2);
    const float r0 = 1.0f / l0, r1 = 1.0f / l1;
    const int row0 = qt * 256 + wg * 64 + w4 * 16 + (lane >> 2);
    bf16* po = g_o + (size_t)row0 * D_MODEL + head * 32 + (lane & 3) * 2;
#pragma unroll
    for (int i = 0; i < 4; i++) {
      *reinterpret_cast<uint32_t*>(po + 8 * i) = pack_bf16(oacc[4 * i] * r0, oacc[4 * i + 1] * r0);
      *reinterpret_cast<uint32_t*>(po + 8 * D_MODEL + 8 * i) = pack_bf16(oacc[4 * i + 2] * r1, oacc[4 * i + 3] * r1);
    }
  }
}

constexpr int G3_STAGES = 6;
constexpr int G3_A_BYTES = 128 * 64 * 2, G3_B_BYTES = 64 * 128 * 2;
constexpr int G3_STAGE_BYTES = G3_A_BYTES + G3_B_BYTES;
constexpr int G3_SMEM = G3_STAGES * G3_STAGE_BYTES + 1024 + 256;
constexpr int G3_KSTEPS = 16 + 56;

__global__ void __cluster_dims__(2, 1, 1) __launch_bounds__(384, 1)
gemm3_kernel(const __grid_constant__ CUtensorMap tmO, const __grid_constant__ CUtensorMap tmH,
             const __grid_constant__ CUtensorMap tmWo, const __grid_constant__ CUtensorMap tmWd,
             const bf16* __restrict__ x, bf16* __restrict__ out) {
  extern __shared__ uint8_t smem_raw[];
  const uint32_t base = (smem_u32(smem_raw) + 1023) & ~1023u;
  const uint32_t sA = base, sB = base + G3_STAGES * G3_A_BYTES;
  const uint32_t bars = sB + G3_STAGES * G3_B_BYTES;
  auto full = [&](int s) { return bars + 8 * s; };
  auto empty = [&](int s) { return bars + 8 * (G3_STAGES + s); };
  const uint32_t rank = cluster_rank();
  const int wg = threadIdx.x >> 7;
  if (threadIdx.x == 0) {
    for (int s = 0; s < G3_STAGES; s++) { mbar_init(full(s), 1); mbar_init(empty(s), 4); }
    asm volatile("fence.mbarrier_init.release.cluster;" ::: "memory");
    asm volatile("fence.proxy.async.shared::cta;" ::: "memory");
  }
  __syncthreads();
  cluster_sync_all();
  const int mp = (blockIdx.x >> 1) & 7, nt = blockIdx.x >> 4;
  const int m0 = (mp * 2 + rank) * 128, n0 = nt * 128;
  if (wg == 0) {
    reg_dec<40>();
    if (threadIdx.x == 0) {
      int s = 0; uint32_t ph = 0;
      for (int k = 0; k < G3_KSTEPS; k++) {
        const bool p1 = k < 16;
        const int kc = (p1 ? k : k - 16) * 64;
        mbar_wait(empty(s), ph ^ 1);
        mbar_expect_tx(full(s), G3_STAGE_BYTES);
        tma_load_2d(sA + s * G3_A_BYTES, p1 ? &tmO : &tmH, full(s), kc, m0);
        tma_load_2d_mc(sB + s * G3_B_BYTES + rank * 8192, p1 ? &tmWo : &tmWd, full(s), n0 + rank * 64, kc, 3);
        if (++s == G3_STAGES) { s = 0; ph ^= 1; }
      }
    }
    __syncwarp();
    cluster_sync_all();
  } else {
    reg_inc<232>();
    const int cw = wg - 1;
    const int tid = threadIdx.x & 127, lane = tid & 31, w4 = tid >> 5;
    float acc[64];
    uint32_t spk[32];
    int s = 0; uint32_t ph = 0; int prev_s = 0;
    for (int k = 0; k < G3_KSTEPS; k++) {
      mbar_wait(full(s), ph);
      wgmma_fence();
      const uint64_t da = make_desc(sA + s * G3_A_BYTES + cw * 8192, 16, 1024, 1);
      const uint64_t db = make_desc(sB + s * G3_B_BYTES, 8192, 1024, 1);
      const bool first = (k == 0) || (k == 16);
#pragma unroll
      for (int kk = 0; kk < 4; kk++) wgmma_ss_n128<1>(acc, da + kk * 2, db + kk * 128, !(first && kk == 0));
      wgmma_commit();
      if (k == 15) {
        wgmma_wait<0>();
        if (tid < 2) { mbar_arrive_cluster(empty(prev_s), tid); mbar_arrive_cluster(empty(s), tid); }
#pragma unroll
        for (int i = 0; i < 32; i++) spk[i] = pack_bf16(acc[2 * i], acc[2 * i + 1]);
      } else if (k > 0 && k != 16) {
        wgmma_wait<1>();
        if (tid < 2) mbar_arrive_cluster(empty(prev_s), tid);
      }
      prev_s = s;
      if (++s == G3_STAGES) { s = 0; ph ^= 1; }
    }
    wgmma_wait<0>();
    if (tid < 2) mbar_arrive_cluster(empty(prev_s), tid);
    const int row0 = m0 + cw * 64 + w4 * 16 + (lane >> 2);
    const size_t off0 = (size_t)row0 * D_MODEL + n0 + (lane & 3) * 2;
#pragma unroll
    for (int j = 0; j < 16; j++) {
#pragma unroll
      for (int hh = 0; hh < 2; hh++) {
        const size_t off = off0 + (size_t)hh * 8 * D_MODEL + 8 * j;
        const uint32_t xv = *reinterpret_cast<const uint32_t*>(x + off);
        const uint32_t sv = spk[2 * j + hh];
        float r[2], y[2], gt[2];
        y[0] = acc[4 * j + 2 * hh]; y[1] = acc[4 * j + 2 * hh + 1];
        round_pair(y[0], y[1]);
#pragma unroll
        for (int e = 0; e < 2; e++) gt[e] = y[e] * rcp(1.0f + ex2(-y[e] * 1.4426950408889634f));
        round_pair(gt[0], gt[1]);
        gt[0] *= __uint_as_float(sv << 16); gt[1] *= __uint_as_float(sv & 0xffff0000u);
        round_pair(gt[0], gt[1]);
        r[0] = __uint_as_float(xv << 16) + gt[0]; r[1] = __uint_as_float(xv & 0xffff0000u) + gt[1];
        *reinterpret_cast<uint32_t*>(out + off) = pack_bf16(r[0], r[1]);
      }
    }
    cluster_sync_all();
  }
}

typedef CUresult (*PFN_encodeTiled_t)(CUtensorMap*, CUtensorMapDataType, cuuint32_t, void*, const cuuint64_t*,
                                      const cuuint64_t*, const cuuint32_t*, const cuuint32_t*, CUtensorMapInterleave,
                                      CUtensorMapSwizzle, CUtensorMapL2promotion, CUtensorMapFloatOOBfill);

static CUtensorMap make_map(PFN_encodeTiled_t fn, const void* ptr, uint64_t rows, uint64_t cols, uint32_t box_cols,
                            uint32_t box_rows, CUtensorMapSwizzle swz) {
  CUtensorMap m;
  cuuint64_t dims[2] = {cols, rows};
  cuuint64_t strides[1] = {cols * 2};
  cuuint32_t box[2] = {box_cols, box_rows};
  cuuint32_t es[2] = {1, 1};
  fn(&m, CU_TENSOR_MAP_DATA_TYPE_BFLOAT16, 2, const_cast<void*>(ptr), dims, strides, box, es,
     CU_TENSOR_MAP_INTERLEAVE_NONE, swz, CU_TENSOR_MAP_L2_PROMOTION_L2_128B, CU_TENSOR_MAP_FLOAT_OOB_FILL_NONE);
  return m;
}

extern "C" void kernel_launch(void* const* d_in, const int* in_sizes, int n_in, void* d_out, int out_size) {
  const bf16* x = (const bf16*)d_in[0];
  const bf16* wqkv = (const bf16*)d_in[1];
  const bf16* wo = (const bf16*)d_in[2];
  const bf16* wg = (const bf16*)d_in[4];
  const bf16* wu = (const bf16*)d_in[5];
  const bf16* wd = (const bf16*)d_in[6];
  bf16* out = (bf16*)d_out;

  static PFN_encodeTiled_t enc = nullptr;
  if (!enc) {
    void* fp = nullptr;
    cudaDriverEntryPointQueryResult qr;
    cudaGetDriverEntryPoint("cuTensorMapEncodeTiled", &fp, cudaEnableDefault, &qr);
    enc = (PFN_encodeTiled_t)fp;
  }
  void *p_xn, *p_qkv, *p_h, *p_o;
  cudaGetSymbolAddress(&p_xn, g_xn);
  cudaGetSymbolAddress(&p_qkv, g_qkv);
  cudaGetSymbolAddress(&p_h, g_h);
  cudaGetSymbolAddress(&p_o, g_o);

  const CUtensorMap tmXn = make_map(enc, p_xn, S_LEN, D_MODEL, 64, 128, CU_TENSOR_MAP_SWIZZLE_128B);
  const CUtensorMap tmWqkv = make_map(enc, wqkv, D_MODEL, 3 * D_MODEL, 64, 64, CU_TENSOR_MAP_SWIZZLE_128B);
  const CUtensorMap tmWg = make_map(enc, wg, D_MODEL, F_DIM, 64, 64, CU_TENSOR_MAP_SWIZZLE_128B);
  const CUtensorMap tmWu = make_map(enc, wu, D_MODEL, F_DIM, 64, 64, CU_TENSOR_MAP_SWIZZLE_128B);
  const CUtensorMap tmQKV = make_map(enc, p_qkv, 3 * N_HEADS * S_LEN, 32, 32, 128, CU_TENSOR_MAP_SWIZZLE_64B);
  const CUtensorMap tmO = make_map(enc, p_o, S_LEN, D_MODEL, 64, 128, CU_TENSOR_MAP_SWIZZLE_128B);
  const CUtensorMap tmH = make_map(enc, p_h, S_LEN, F_DIM, 64, 128, CU_TENSOR_MAP_SWIZZLE_128B);
  const CUtensorMap tmWo = make_map(enc, wo, D_MODEL, D_MODEL, 64, 64, CU_TENSOR_MAP_SWIZZLE_128B);
  const CUtensorMap tmWd = make_map(enc, wd, F_DIM, D_MODEL, 64, 64, CU_TENSOR_MAP_SWIZZLE_128B);

  cudaFuncSetAttribute(gemm1_kernel, cudaFuncAttributeMaxDynamicSharedMemorySize, G1_SMEM);
  cudaFuncSetAttribute(attn_kernel, cudaFuncAttributeMaxDynamicSharedMemorySize, AT_SMEM);
  cudaFuncSetAttribute(gemm3_kernel, cudaFuncAttributeMaxDynamicSharedMemorySize, G3_SMEM);

  ln_kernel<<<S_LEN / 8, 256>>>(x);
  gemm1_kernel<<<132, 384, G1_SMEM>>>(tmXn, tmWqkv, tmWg, tmWu);
  attn_kernel<<<256, 512, AT_SMEM>>>(tmQKV);
  gemm3_kernel<<<128, 384, G3_SMEM>>>(tmO, tmH, tmWo, tmWd, x, out);
}
```
